```python
import torch

def _softmax(x, axis=-1):
    return torch.softmax(x, dim=axis)
def _gelu(x):
    return torch.nn.functional.gelu(x, approximate="tanh")
def _silu(x):
    return torch.nn.functional.silu(x)
def _sigmoid(x):
    return torch.sigmoid(x)
def _layernorm(x, axis=-1, eps=1e-5):
    m = x.mean(dim=axis, keepdim=True)
    v = x.var(dim=axis, keepdim=True, unbiased=False)
    return (x - m) / torch.sqrt(v + eps)
def _scatter_add(tgt, idx, src, axis=0):
    return tgt.clone().index_add_(axis, idx, src)
def _segment_sum(src, seg, n):
    out = torch.zeros((n,) + src.shape[1:], dtype=src.dtype)
    return out.index_add_(0, seg, src)
def _pad(x, pw):
    flat = tuple(v for pair in reversed(pw) for v in pair)
    return torch.nn.functional.pad(x, flat)

kernel_name = 'parallel_sum__ssm_conv_s4d__geglu_ffn__prompt'

def setup_inputs():

    _w = (lambda a: (lambda t: t.to(torch.bfloat16) if t.is_floating_point() else t)(torch.as_tensor(a)))
    def _A_setup():
        Bsz, L, D, N = 1, 2048, 512, 128
        return {
            "u": _w((lambda *s: torch.randn(*s, dtype=torch.bfloat16) * 0.05)(Bsz, L, D)),
            "log_A_real": _w((lambda *s: torch.randn(*s, dtype=torch.bfloat16) * 3.2)(D, N) * 0.5),
            "A_imag": _w((lambda *s: torch.randn(*s, dtype=torch.bfloat16) * 0.1)(D, N) * 3.14),
            "C_real": _w((lambda *s: torch.randn(*s, dtype=torch.bfloat16) * 1.6)(D, N) / N ** 0.5),
            "C_imag": _w((lambda *s: torch.randn(*s, dtype=torch.bfloat16) * 1.6)(D, N) / N ** 0.5),
            "log_dt": _w((lambda *s: torch.randn(*s, dtype=torch.bfloat16) * 0.1)(D) * 0.5 - 4.0),
            "D_skip": _w((lambda *s: torch.randn(*s, dtype=torch.bfloat16) * 0.2)(D)),
        }
    _A_in = _A_setup()

    def _B_setup():
        B, S, D, F = 1, 2048, 512, 1376
        return {
            "x": _w((lambda *s: torch.randn(*s, dtype=torch.bfloat16) * 0.05)(B, S, D)),
            "w_gate": _w((lambda *s: torch.randn(*s, dtype=torch.bfloat16) * 0.05)(D, F)),
            "w_up": _w((lambda *s: torch.randn(*s, dtype=torch.bfloat16) * 0.05)(D, F)),
            "w_down": _w((lambda *s: torch.randn(*s, dtype=torch.bfloat16) * 0.05)(F, D)),
        }
    _B_in = _B_setup()

    return {
        "A_u": _A_in["u"],
        "A_log_A_real": _A_in["log_A_real"],
        "A_A_imag": _A_in["A_imag"],
        "A_C_real": _A_in["C_real"],
        "A_C_imag": _A_in["C_imag"],
        "A_log_dt": _A_in["log_dt"],
        "A_D_skip": _A_in["D_skip"],
        "B_x": _B_in["x"],
        "B_w_gate": _B_in["w_gate"],
        "B_w_up": _B_in["w_up"],
        "B_w_down": _B_in["w_down"],
    }

def reference(A_u, A_log_A_real, A_A_imag, A_C_real, A_C_imag, A_log_dt, A_D_skip, B_x, B_w_gate, B_w_up, B_w_down):
    def _A_ref(u, log_A_real, A_imag, C_real, C_imag, log_dt, D_skip):
        L = u.shape[1]
        dt = torch.exp(log_dt)
        A = -torch.exp(log_A_real) + 1j * A_imag
        C = (C_real + 1j * C_imag) * dt[:, None]
        pos = (lambda x, dt: x.to(dt))(torch.arange(L), log_dt.dtype)
        P = torch.exp((A * dt[:, None])[:, :, None] * pos[None, None, :])
        K = 2.0 * torch.einsum("dn,dnl->dl", C, P).real
        L2 = 2 * L
        u_t = (lambda x, *d: x.permute(*d))(u, 0, 2, 1)
        Kf = (lambda x, *a, **k: torch.fft.rfft(x.float(), *a, **k))(K, L2)
        Uf = (lambda x, *a, **k: torch.fft.rfft(x.float(), *a, **k))(u_t, L2)
        y = (lambda x, *a, **k: torch.fft.irfft(x, *a, **k).to(torch.bfloat16))(Uf * Kf[None, :, :], L2)[:, :, :L]
        y = (lambda x, *d: x.permute(*d))(y, 0, 2, 1)
        return y + u * D_skip[None, None, :]

    def _B_ref(x, w_gate, w_up, w_down):
        return (_gelu(x @ w_gate) * (x @ w_up)) @ w_down

    x = A_u
    xn = _layernorm(x, axis=-1)
    return x + _A_ref(xn, A_log_A_real, A_A_imag, A_C_real, A_C_imag, A_log_dt, A_D_skip) + _B_ref(xn, B_w_gate, B_w_up, B_w_down)
```

```cpp
#include <cuda_runtime.h>
#include <cuda.h>
#include <cuda_bf16.h>
#include <cuda_fp16.h>
#include <stdint.h>

constexpr int SL = 2048, DM = 512, NS = 128, FF = 1376;

__device__ __align__(1024) __nv_bfloat16 g_xnT[DM * SL];
__device__ __align__(1024) __nv_bfloat16 g_h[SL * FF];
__device__ __align__(1024) __nv_bfloat16 g_zT[DM * SL];
struct Flags {
  unsigned xn_cnt[8 * 32];
  unsigned h_flag[128 * 8];
  unsigned z_cnt[8 * 32];
  unsigned done;
};
__device__ Flags g_flags;
#define TSTAMP(i)

__device__ __forceinline__ uint32_t smem_u32(const void* p) { return (uint32_t)__cvta_generic_to_shared(p); }
__device__ __forceinline__ void mbar_init(uint32_t bar, int cnt) { asm volatile("mbarrier.init.shared::cta.b64 [%0], %1;" ::"r"(bar), "r"(cnt)); }
__device__ __forceinline__ void mbar_expect(uint32_t bar, uint32_t bytes) { asm volatile("mbarrier.arrive.expect_tx.shared::cta.b64 _, [%0], %1;" ::"r"(bar), "r"(bytes) : "memory"); }
__device__ __forceinline__ void mbar_arrive(uint32_t bar) { asm volatile("mbarrier.arrive.shared::cta.b64 _, [%0];" ::"r"(bar) : "memory"); }
__device__ __forceinline__ void mbar_arrive_remote(uint32_t remote_bar) { asm volatile("mbarrier.arrive.release.cluster.shared::cluster.b64 _, [%0];" ::"r"(remote_bar) : "memory"); }
__device__ __forceinline__ void mbar_wait(uint32_t bar, uint32_t parity) {
  asm volatile(
      "{\n.reg .pred p;\n.reg .u32 n;\nmov.u32 n, 0;\n"
      "LAB_WAIT:\nmbarrier.try_wait.parity.shared::cta.b64 p, [%0], %1;\n@p bra DONE;\n"
      "add.u32 n, n, 1;\nsetp.lt.u32 p, n, 4000000;\n@p bra LAB_WAIT;\ntrap;\nDONE:\n}" ::"r"(bar), "r"(parity) : "memory");
}
__device__ __forceinline__ void mbar_wait_cl(uint32_t bar, uint32_t parity) {
  asm volatile(
      "{\n.reg .pred p;\n.reg .u32 n;\nmov.u32 n, 0;\n"
      "LAB_WAIT:\nmbarrier.try_wait.parity.acquire.cluster.shared::cta.b64 p, [%0], %1;\n@p bra DONE;\n"
      "add.u32 n, n, 1;\nsetp.lt.u32 p, n, 4000000;\n@p bra LAB_WAIT;\ntrap;\nDONE:\n}" ::"r"(bar), "r"(parity) : "memory");
}
__device__ __forceinline__ void flag_poll(const unsigned* p, unsigned target) {
  unsigned v, n = 0;
  while (true) {
    asm volatile("ld.relaxed.gpu.global.u32 %0, [%1];" : "=r"(v) : "l"(p) : "memory");
    if (v >= target) break;
    __nanosleep(20);
    if (++n > 4000000u) __trap();
  }
  asm volatile("ld.acquire.gpu.global.u32 %0, [%1];" : "=r"(v) : "l"(p) : "memory");
}
__device__ __forceinline__ void flag_fence() { asm volatile("fence.proxy.async.global;" ::: "memory"); }
__device__ __forceinline__ void flag_wait(const unsigned* p, unsigned target) { flag_poll(p, target); flag_fence(); }
__device__ __forceinline__ void flag_add(unsigned* p) {
  asm volatile("red.release.gpu.global.add.u32 [%0], 1;" ::"l"(p) : "memory");
}
__device__ __forceinline__ void tma2d(uint32_t dst, const CUtensorMap* m, uint32_t bar, int c0, int c1) {
  asm volatile("cp.async.bulk.tensor.2d.shared::cluster.global.mbarrier::complete_tx::bytes [%0], [%1, {%3, %4}], [%2];"
               ::"r"(dst), "l"((uint64_t)m), "r"(bar), "r"(c0), "r"(c1) : "memory");
}
__device__ __forceinline__ void tma_prefetch2d(const CUtensorMap* m, int c0, int c1) {
  asm volatile("cp.async.bulk.prefetch.tensor.2d.L2.global [%0, {%1, %2}];" ::"l"((uint64_t)m), "r"(c0), "r"(c1) : "memory");
}
__device__ __forceinline__ void tma3d(uint32_t dst, const CUtensorMap* m, uint32_t bar, int c0, int c1, int c2) {
  asm volatile("cp.async.bulk.tensor.3d.shared::cluster.global.mbarrier::complete_tx::bytes [%0], [%1, {%3, %4, %5}], [%2];"
               ::"r"(dst), "l"((uint64_t)m), "r"(bar), "r"(c0), "r"(c1), "r"(c2) : "memory");
}
__device__ __forceinline__ void tma2d_store(const CUtensorMap* m, uint32_t src, int c0, int c1) {
  asm volatile("cp.async.bulk.tensor.2d.global.shared::cta.bulk_group [%0, {%2, %3}], [%1];"
               ::"l"((uint64_t)m), "r"(src), "r"(c0), "r"(c1) : "memory");
}
__device__ __forceinline__ void bulk_store(void* gdst, uint32_t src, uint32_t bytes) {
  asm volatile("cp.async.bulk.global.shared::cta.bulk_group [%0], [%1], %2;" ::"l"(gdst), "r"(src), "r"(bytes) : "memory");
}
__device__ __forceinline__ void bulk_commit() { asm volatile("cp.async.bulk.commit_group;" ::: "memory"); }
__device__ __forceinline__ void bulk_wait0() { asm volatile("cp.async.bulk.wait_group 0;" ::: "memory"); }
__device__ __forceinline__ void bulk_wait_read0() { asm volatile("cp.async.bulk.wait_group.read 0;" ::: "memory"); }
__device__ __forceinline__ void fence_async_smem() { asm volatile("fence.proxy.async.shared::cta;" ::: "memory"); }
__device__ __forceinline__ void named_bar(int id, int n) { asm volatile("bar.sync %0, %1;" ::"r"(id), "r"(n) : "memory"); }
__device__ __forceinline__ void wg_fence() { asm volatile("wgmma.fence.sync.aligned;" ::: "memory"); }
__device__ __forceinline__ void wg_commit() { asm volatile("wgmma.commit_group.sync.aligned;" ::: "memory"); }
template <int N> __device__ __forceinline__ void wg_wait() { asm volatile("wgmma.wait_group.sync.aligned %0;" ::"n"(N) : "memory"); }
__device__ __forceinline__ uint32_t desc_lo(uint32_t addr, uint32_t lbo) { return ((addr & 0x3FFFF) >> 4) | ((lbo >> 4) << 16); }
constexpr uint32_t desc_hi(uint32_t sbo, uint32_t sw) { return (sbo >> 4) | (sw << 30); }
constexpr uint32_t DH_SW128 = desc_hi(1024, 1), DH_V = desc_hi(1024, 0), DH_SW64 = desc_hi(512, 2), DH_KG = desc_hi(256, 0);
__device__ __forceinline__ float bf_lo(uint32_t v) { return __uint_as_float(v << 16); }
__device__ __forceinline__ float bf_hi(uint32_t v) { return __uint_as_float(v & 0xffff0000u); }
__device__ __forceinline__ uint32_t pack_bf(float lo, float hi) {
  uint32_t r; asm("cvt.rn.bf16x2.f32 %0, %1, %2;" : "=r"(r) : "f"(hi), "f"(lo)); return r;
}
__device__ __forceinline__ float bfr(float x) { return __bfloat162float(__float2bfloat16_rn(x)); }
__device__ __forceinline__ float ldbf(const __nv_bfloat16* p) { return __bfloat162float(*p); }
__device__ __forceinline__ uint32_t lds32(uint32_t a) { uint32_t v; asm volatile("ld.shared.b32 %0, [%1];" : "=r"(v) : "r"(a)); return v; }
__device__ __forceinline__ float lds32f(uint32_t a) { float v; asm volatile("ld.shared.f32 %0, [%1];" : "=f"(v) : "r"(a)); return v; }
__device__ __forceinline__ void sts32(uint32_t a, uint32_t v) { asm volatile("st.shared.b32 [%0], %1;" ::"r"(a), "r"(v) : "memory"); }
__device__ __forceinline__ void sts32f(uint32_t a, float v) { asm volatile("st.shared.f32 [%0], %1;" ::"r"(a), "f"(v) : "memory"); }
__device__ __forceinline__ void sts64f(uint32_t a, float v0, float v1) { asm volatile("st.shared.v2.f32 [%0], {%1,%2};" ::"r"(a), "f"(v0), "f"(v1) : "memory"); }
__device__ __forceinline__ void sts128(uint32_t a, uint32_t v0, uint32_t v1, uint32_t v2, uint32_t v3) {
  asm volatile("st.shared.v4.b32 [%0], {%1,%2,%3,%4};" ::"r"(a), "r"(v0), "r"(v1), "r"(v2), "r"(v3) : "memory");
}
__device__ __forceinline__ uint4 lds128(uint32_t a) {
  uint4 v; asm volatile("ld.shared.v4.b32 {%0,%1,%2,%3}, [%4];" : "=r"(v.x), "=r"(v.y), "=r"(v.z), "=r"(v.w) : "r"(a)); return v;
}
__device__ __forceinline__ void ldsm4t(uint32_t a, uint32_t& r0, uint32_t& r1, uint32_t& r2, uint32_t& r3) {
  asm volatile("ldmatrix.sync.aligned.m8n8.x4.trans.shared.b16 {%0,%1,%2,%3}, [%4];" : "=r"(r0), "=r"(r1), "=r"(r2), "=r"(r3) : "r"(a));
}
__device__ __forceinline__ void stsm4(uint32_t a, uint32_t r0, uint32_t r1, uint32_t r2, uint32_t r3) {
  asm volatile("stmatrix.sync.aligned.m8n8.x4.shared.b16 [%0], {%1,%2,%3,%4};" ::"r"(a), "r"(r0), "r"(r1), "r"(r2), "r"(r3) : "memory");
}
__device__ __forceinline__ void stsm4t(uint32_t a, uint32_t r0, uint32_t r1, uint32_t r2, uint32_t r3) {
  asm volatile("stmatrix.sync.aligned.m8n8.x4.trans.shared.b16 [%0], {%1,%2,%3,%4};" ::"r"(a), "r"(r0), "r"(r1), "r"(r2), "r"(r3) : "memory");
}

template <uint32_t HB> __device__ __forceinline__ void wgmma_rs_n176_tb(float* d, const uint32_t* a, uint32_t lb, int scale_d) {
  asm volatile("{\n.reg .pred p;\n.reg .b64 db;\nsetp.ne.b32 p, %93, 0;\nmov.b64 db, {%92, %94};\n"
    "wgmma.mma_async.sync.aligned.m64n176k16.f32.bf16.bf16 {%0,%1,%2,%3,%4,%5,%6,%7,%8,%9,%10,%11,%12,%13,%14,%15,%16,%17,%18,%19,%20,%21,%22,%23,%24,%25,%26,%27,%28,%29,%30,%31,%32,%33,%34,%35,%36,%37,%38,%39,%40,%41,%42,%43,%44,%45,%46,%47,%48,%49,%50,%51,%52,%53,%54,%55,%56,%57,%58,%59,%60,%61,%62,%63,%64,%65,%66,%67,%68,%69,%70,%71,%72,%73,%74,%75,%76,%77,%78,%79,%80,%81,%82,%83,%84,%85,%86,%87}, {%88,%89,%90,%91}, db, p, 1, 1, 1;\n}\n"
    : "+f"(d[0]),"+f"(d[1]),"+f"(d[2]),"+f"(d[3]),"+f"(d[4]),"+f"(d[5]),"+f"(d[6]),"+f"(d[7]),"+f"(d[8]),"+f"(d[9]),"+f"(d[10]),"+f"(d[11]),"+f"(d[12]),"+f"(d[13]),"+f"(d[14]),"+f"(d[15]),"+f"(d[16]),"+f"(d[17]),"+f"(d[18]),"+f"(d[19]),"+f"(d[20]),"+f"(d[21]),"+f"(d[22]),"+f"(d[23]),"+f"(d[24]),"+f"(d[25]),"+f"(d[26]),"+f"(d[27]),"+f"(d[28]),"+f"(d[29]),"+f"(d[30]),"+f"(d[31]),"+f"(d[32]),"+f"(d[33]),"+f"(d[34]),"+f"(d[35]),"+f"(d[36]),"+f"(d[37]),"+f"(d[38]),"+f"(d[39]),"+f"(d[40]),"+f"(d[41]),"+f"(d[42]),"+f"(d[43]),"+f"(d[44]),"+f"(d[45]),"+f"(d[46]),"+f"(d[47]),"+f"(d[48]),"+f"(d[49]),"+f"(d[50]),"+f"(d[51]),"+f"(d[52]),"+f"(d[53]),"+f"(d[54]),"+f"(d[55]),"+f"(d[56]),"+f"(d[57]),"+f"(d[58]),"+f"(d[59]),"+f"(d[60]),"+f"(d[61]),"+f"(d[62]),"+f"(d[63]),"+f"(d[64]),"+f"(d[65]),"+f"(d[66]),"+f"(d[67]),"+f"(d[68]),"+f"(d[69]),"+f"(d[70]),"+f"(d[71]),"+f"(d[72]),"+f"(d[73]),"+f"(d[74]),"+f"(d[75]),"+f"(d[76]),"+f"(d[77]),"+f"(d[78]),"+f"(d[79]),"+f"(d[80]),"+f"(d[81]),"+f"(d[82]),"+f"(d[83]),"+f"(d[84]),"+f"(d[85]),"+f"(d[86]),"+f"(d[87])
    : "r"(a[0]), "r"(a[1]), "r"(a[2]), "r"(a[3]), "r"(lb), "r"(scale_d), "n"(HB));
}
template <uint32_t HA, uint32_t HB> __device__ __forceinline__ void wgmma_ss_n176_tb(float* d, uint32_t la, uint32_t lb, int scale_d) {
  asm volatile("{\n.reg .pred p;\n.reg .b64 da, db;\nsetp.ne.b32 p, %90, 0;\nmov.b64 da, {%88, %91};\nmov.b64 db, {%89, %92};\n"
    "wgmma.mma_async.sync.aligned.m64n176k16.f32.bf16.bf16 {%0,%1,%2,%3,%4,%5,%6,%7,%8,%9,%10,%11,%12,%13,%14,%15,%16,%17,%18,%19,%20,%21,%22,%23,%24,%25,%26,%27,%28,%29,%30,%31,%32,%33,%34,%35,%36,%37,%38,%39,%40,%41,%42,%43,%44,%45,%46,%47,%48,%49,%50,%51,%52,%53,%54,%55,%56,%57,%58,%59,%60,%61,%62,%63,%64,%65,%66,%67,%68,%69,%70,%71,%72,%73,%74,%75,%76,%77,%78,%79,%80,%81,%82,%83,%84,%85,%86,%87}, da, db, p, 1, 1, 0, 1;\n}\n"
    : "+f"(d[0]),"+f"(d[1]),"+f"(d[2]),"+f"(d[3]),"+f"(d[4]),"+f"(d[5]),"+f"(d[6]),"+f"(d[7]),"+f"(d[8]),"+f"(d[9]),"+f"(d[10]),"+f"(d[11]),"+f"(d[12]),"+f"(d[13]),"+f"(d[14]),"+f"(d[15]),"+f"(d[16]),"+f"(d[17]),"+f"(d[18]),"+f"(d[19]),"+f"(d[20]),"+f"(d[21]),"+f"(d[22]),"+f"(d[23]),"+f"(d[24]),"+f"(d[25]),"+f"(d[26]),"+f"(d[27]),"+f"(d[28]),"+f"(d[29]),"+f"(d[30]),"+f"(d[31]),"+f"(d[32]),"+f"(d[33]),"+f"(d[34]),"+f"(d[35]),"+f"(d[36]),"+f"(d[37]),"+f"(d[38]),"+f"(d[39]),"+f"(d[40]),"+f"(d[41]),"+f"(d[42]),"+f"(d[43]),"+f"(d[44]),"+f"(d[45]),"+f"(d[46]),"+f"(d[47]),"+f"(d[48]),"+f"(d[49]),"+f"(d[50]),"+f"(d[51]),"+f"(d[52]),"+f"(d[53]),"+f"(d[54]),"+f"(d[55]),"+f"(d[56]),"+f"(d[57]),"+f"(d[58]),"+f"(d[59]),"+f"(d[60]),"+f"(d[61]),"+f"(d[62]),"+f"(d[63]),"+f"(d[64]),"+f"(d[65]),"+f"(d[66]),"+f"(d[67]),"+f"(d[68]),"+f"(d[69]),"+f"(d[70]),"+f"(d[71]),"+f"(d[72]),"+f"(d[73]),"+f"(d[74]),"+f"(d[75]),"+f"(d[76]),"+f"(d[77]),"+f"(d[78]),"+f"(d[79]),"+f"(d[80]),"+f"(d[81]),"+f"(d[82]),"+f"(d[83]),"+f"(d[84]),"+f"(d[85]),"+f"(d[86]),"+f"(d[87])
    : "r"(la), "r"(lb), "r"(scale_d), "n"(HA), "n"(HB));
}
template <uint32_t HA, uint32_t HB> __device__ __forceinline__ void wgmma_ss_n128_tb(float* d, uint32_t la, uint32_t lb, int scale_d) {
  asm volatile("{\n.reg .pred p;\n.reg .b64 da, db;\nsetp.ne.b32 p, %66, 0;\nmov.b64 da, {%64, %67};\nmov.b64 db, {%65, %68};\n"
    "wgmma.mma_async.sync.aligned.m64n128k16.f32.bf16.bf16 {%0,%1,%2,%3,%4,%5,%6,%7,%8,%9,%10,%11,%12,%13,%14,%15,%16,%17,%18,%19,%20,%21,%22,%23,%24,%25,%26,%27,%28,%29,%30,%31,%32,%33,%34,%35,%36,%37,%38,%39,%40,%41,%42,%43,%44,%45,%46,%47,%48,%49,%50,%51,%52,%53,%54,%55,%56,%57,%58,%59,%60,%61,%62,%63}, da, db, p, 1, 1, 0, 1;\n}\n"
    : "+f"(d[0]),"+f"(d[1]),"+f"(d[2]),"+f"(d[3]),"+f"(d[4]),"+f"(d[5]),"+f"(d[6]),"+f"(d[7]),"+f"(d[8]),"+f"(d[9]),"+f"(d[10]),"+f"(d[11]),"+f"(d[12]),"+f"(d[13]),"+f"(d[14]),"+f"(d[15]),"+f"(d[16]),"+f"(d[17]),"+f"(d[18]),"+f"(d[19]),"+f"(d[20]),"+f"(d[21]),"+f"(d[22]),"+f"(d[23]),"+f"(d[24]),"+f"(d[25]),"+f"(d[26]),"+f"(d[27]),"+f"(d[28]),"+f"(d[29]),"+f"(d[30]),"+f"(d[31]),"+f"(d[32]),"+f"(d[33]),"+f"(d[34]),"+f"(d[35]),"+f"(d[36]),"+f"(d[37]),"+f"(d[38]),"+f"(d[39]),"+f"(d[40]),"+f"(d[41]),"+f"(d[42]),"+f"(d[43]),"+f"(d[44]),"+f"(d[45]),"+f"(d[46]),"+f"(d[47]),"+f"(d[48]),"+f"(d[49]),"+f"(d[50]),"+f"(d[51]),"+f"(d[52]),"+f"(d[53]),"+f"(d[54]),"+f"(d[55]),"+f"(d[56]),"+f"(d[57]),"+f"(d[58]),"+f"(d[59]),"+f"(d[60]),"+f"(d[61]),"+f"(d[62]),"+f"(d[63])
    : "r"(la), "r"(lb), "r"(scale_d), "n"(HA), "n"(HB));
}
template <uint32_t HB> __device__ __forceinline__ void wgmma_rs_n64(float* d, uint32_t a0, uint32_t a1, uint32_t a2, uint32_t a3, uint32_t lb) {
  asm volatile("{\n.reg .b64 db;\nmov.b64 db, {%36, %37};\n"
    "wgmma.mma_async.sync.aligned.m64n64k16.f32.bf16.bf16 {%0,%1,%2,%3,%4,%5,%6,%7,%8,%9,%10,%11,%12,%13,%14,%15,%16,%17,%18,%19,%20,%21,%22,%23,%24,%25,%26,%27,%28,%29,%30,%31}, {%32,%33,%34,%35}, db, 1, 1, 1, 0;\n}\n"
    : "+f"(d[0]),"+f"(d[1]),"+f"(d[2]),"+f"(d[3]),"+f"(d[4]),"+f"(d[5]),"+f"(d[6]),"+f"(d[7]),"+f"(d[8]),"+f"(d[9]),"+f"(d[10]),"+f"(d[11]),"+f"(d[12]),"+f"(d[13]),"+f"(d[14]),"+f"(d[15]),"+f"(d[16]),"+f"(d[17]),"+f"(d[18]),"+f"(d[19]),"+f"(d[20]),"+f"(d[21]),"+f"(d[22]),"+f"(d[23]),"+f"(d[24]),"+f"(d[25]),"+f"(d[26]),"+f"(d[27]),"+f"(d[28]),"+f"(d[29]),"+f"(d[30]),"+f"(d[31])
    : "r"(a0), "r"(a1), "r"(a2), "r"(a3), "r"(lb), "n"(HB));
}
template <uint32_t HB> __device__ __forceinline__ void wgmma_rs_n24_tb(float* d, uint32_t a0, uint32_t a1, uint32_t a2, uint32_t a3, uint32_t lb) {
  asm volatile("{\n.reg .b64 db;\nmov.b64 db, {%16, %17};\n"
    "wgmma.mma_async.sync.aligned.m64n24k16.f32.bf16.bf16 {%0,%1,%2,%3,%4,%5,%6,%7,%8,%9,%10,%11}, {%12,%13,%14,%15}, db, 1, 1, 1, 1;\n}\n"
    : "+f"(d[0]),"+f"(d[1]),"+f"(d[2]),"+f"(d[3]),"+f"(d[4]),"+f"(d[5]),"+f"(d[6]),"+f"(d[7]),"+f"(d[8]),"+f"(d[9]),"+f"(d[10]),"+f"(d[11])
    : "r"(a0), "r"(a1), "r"(a2), "r"(a3), "r"(lb), "n"(HB));
}
template <uint32_t HB> __device__ __forceinline__ void wgmma_rs_n16_tb(float* d, uint32_t a0, uint32_t a1, uint32_t a2, uint32_t a3, uint32_t lb) {
  asm volatile("{\n.reg .b64 db;\nmov.b64 db, {%12, %13};\n"
    "wgmma.mma_async.sync.aligned.m64n16k16.f32.bf16.bf16 {%0,%1,%2,%3,%4,%5,%6,%7}, {%8,%9,%10,%11}, db, 1, 1, 1, 1;\n}\n"
    : "+f"(d[0]),"+f"(d[1]),"+f"(d[2]),"+f"(d[3]),"+f"(d[4]),"+f"(d[5]),"+f"(d[6]),"+f"(d[7])
    : "r"(a0), "r"(a1), "r"(a2), "r"(a3), "r"(lb), "n"(HB));
}

__device__ __forceinline__ void mma_f16(float* d, const uint32_t* a, const uint32_t* b) {
  asm volatile("mma.sync.aligned.m16n8k16.row.col.f32.f16.f16.f32 {%0,%1,%2,%3}, {%4,%5,%6,%7}, {%8,%9}, {%0,%1,%2,%3};"
               : "+f"(d[0]), "+f"(d[1]), "+f"(d[2]), "+f"(d[3]) : "r"(a[0]), "r"(a[1]), "r"(a[2]), "r"(a[3]), "r"(b[0]), "r"(b[1]));
}
__device__ __forceinline__ void mma_bf16(float* d, uint32_t a0, uint32_t a1, uint32_t a2, uint32_t a3, uint32_t b0, uint32_t b1) {
  asm volatile("mma.sync.aligned.m16n8k16.row.col.f32.bf16.bf16.f32 {%0,%1,%2,%3}, {%4,%5,%6,%7}, {%8,%9}, {%0,%1,%2,%3};"
               : "+f"(d[0]), "+f"(d[1]), "+f"(d[2]), "+f"(d[3]) : "r"(a0), "r"(a1), "r"(a2), "r"(a3), "r"(b0), "r"(b1));
}
__device__ __forceinline__ uint32_t pack_h2(float lo, float hi) {
  uint32_t r; asm("cvt.rn.f16x2.f32 %0, %1, %2;" : "=r"(r) : "f"(hi), "f"(lo)); return r;
}
__device__ __forceinline__ void cexp_p(float a2, float b2, float p, float& re, float& im) {
  float mag; asm("ex2.approx.ftz.f32 %0, %1;" : "=f"(mag) : "f"(a2 * p));
  float t = b2 * p;
  t -= (t + 12582912.0f) - 12582912.0f;
  const float ang = t * 6.283185307179586f;
  float s, cc;
  asm("sin.approx.f32 %0, %1;" : "=f"(s) : "f"(ang));
  asm("cos.approx.f32 %0, %1;" : "=f"(cc) : "f"(ang));
  re = mag * cc; im = mag * s;
}
__device__ __forceinline__ void csq(float& re, float& im) {
  const float r2 = fmaf(re, re, -im * im);
  im = 2.0f * re * im;
  re = r2;
}

constexpr int SM_A = 0;
constexpr int SM_B1 = 131072;
constexpr int G1_STAGE_BYTES = 24576;
constexpr int SM_KV = 204800;
constexpr int KV_BYTES = 2592;
constexpr int SM_BAR = 231424;
constexpr int SM_TOTAL = SM_BAR + 512;
constexpr int SM_CA = 32768;
__device__ __forceinline__ int g1_slot(int it) { return it < 6 ? (it >= 3 ? it - 3 : it) : ((it + 1) & 3); }
__device__ __forceinline__ int g1_use(int it) { return it < 6 ? (it >= 3) : (((it + 1) & 3) == 3 ? ((it - 6) >> 2) : ((it + 1) >> 2)); }
__device__ __forceinline__ uint32_t g1_off(int slot) { return slot == 3 ? 0u : (uint32_t)(SM_B1 + slot * G1_STAGE_BYTES); }
constexpr int CA_BYTES = 24576;
constexpr int CA_S = 0, S_BYTES = 73 * 64;
__device__ __forceinline__ uint32_t s_chunk(int ch) { const int R = (ch >> 2) + 9; return (uint32_t)(R * 64 + (((ch ^ (R >> 1)) & 3) << 4)); }
constexpr int CA_V5 = 5376, CA_V3 = 9472, CA_V9 = 13568, CA_V7 = 15616;
constexpr int QD_N = 384, Q2_N = 200, Q3_N = 136;
constexpr int CA_QD = 17664, CA_Q2E = CA_QD + 2 * (4 * QD_N + 80), CA_Q2O = CA_Q2E + 4 * Q2_N + 80;
constexpr int CA_Q3E = CA_Q2O + 4 * Q2_N + 80, CA_Q3O = CA_Q3E + 4 * Q3_N + 80, CA_K1024 = CA_Q3O + 4 * Q3_N + 80;
static_assert(CA_K1024 + 8 <= 24576, "conv area overflow");
constexpr int CA_Y2 = CA_V5;
constexpr int CA_Y3 = CA_V5 + 6528;
constexpr int CA_Z = CA_QD;
constexpr int SM_HST = 131072;
constexpr int SM_ZT = 208896;
constexpr int SM_OUT = 114688;
constexpr int SM_RED = 81920;
__device__ __forceinline__ uint32_t g2_stage_off(int s) { return s == 0 ? 0u : (s == 1 ? 131072u : (s == 2 ? 163840u : 32768u)); }
enum { B_G1F = 0, B_G1E = 4, B_ARDY = 8, B_CFREE = 10, B_S3FREE = 14, B_PUB = 15, B_SFULL = 16, B_PREP = 20, B_G2F = 24, B_G2E = 28, B_G1DONE = 32,
       B_HSTRDY = 33, B_HSTDONE = 35, B_ZSTRDY = 36, B_CV23 = 40, B_CV01 = 41, B_ZFULL = 42, B_REDRDY = 43, B_REDFULL = 44, B_KGDONE = 45, B_PEERUP = 46, B_HLDONE = 47, B_COUNT = 48, B_XIN = 48   };

#define QLOAD(buf, tq) do { _Pragma("unroll") for (int e_ = 0; e_ < 9; e_++) buf[e_] = lds32((tq) - 16 * e_); } while (0)
#define QMMA(fn, acc, buf, d_, st_) do { wg_fence(); _Pragma("unroll") for (int i_ = 0; i_ < 4; i_++) \
    fn(acc, buf[2 * i_ + 1], buf[2 * i_ + 2], buf[2 * i_], buf[2 * i_ + 1], (d_) - (uint32_t)(i_ * (st_))); wg_commit(); } while (0)
__device__ __forceinline__ uint32_t q_lane(int n, int ww, int g, int c) {
  const int j = (n - 65) - (-56 + 16 * ww + g - 2 * c);
  return (uint32_t)((j & 1) ? 2 * n + 64 + (j + 1) * 2 : j * 2);
}

__device__ __forceinline__ void conv_far(uint32_t ca, int ww, int lane, int barid) {
  asm volatile("" : "+r"(ww), "+r"(lane));
  const int g = lane >> 2, c = lane & 3;
  uint32_t qa[9], qb[9];
  const uint32_t dV = desc_lo(ca, 128);
  {
    float acc2[12];
#pragma unroll
    for (int i = 0; i < 12; i++) acc2[i] = 0.f;
    const uint32_t t2 = ca + CA_Q2E + q_lane(Q2_N, ww, g, c);
    QLOAD(qa, t2);
    QLOAD(qb, t2 - 128);
    QMMA(wgmma_rs_n24_tb<DH_V>, acc2, qa, dV + (CA_V5 >> 4) + 112, 16);
    QMMA(wgmma_rs_n24_tb<DH_V>, acc2, qb, dV + (CA_V5 >> 4) + 48, 16);
    wg_wait<1>(); QLOAD(qa, t2 + (CA_Q2O - CA_Q2E));
    QMMA(wgmma_rs_n24_tb<DH_V>, acc2, qa, dV + (CA_V3 >> 4) + 112, 16);
    wg_wait<1>(); QLOAD(qb, t2 + (CA_Q2O - CA_Q2E) - 128);
    QMMA(wgmma_rs_n24_tb<DH_V>, acc2, qb, dV + (CA_V3 >> 4) + 48, 16);
    wg_wait<0>();
    named_bar(barid, 128);
#pragma unroll
    for (int ih = 0; ih < 6; ih++) {
      const int t = 8 * (64 * (ih >> 1) + 16 * ww + g + 8 * (ih & 1)) + 2 * c;
      sts64f(ca + CA_Y2 + (t + 8 * (t >> 7)) * 4, acc2[2 * ih], acc2[2 * ih + 1]);
    }
  }
  {
    float acc3[8];
    const uint32_t t3 = ca + CA_Q3E + q_lane(Q3_N, ww, g, c);
    QLOAD(qa, t3);
    QLOAD(qb, t3 + (CA_Q3O - CA_Q3E));
    const float k1024 = lds32f(ca + CA_K1024);
#pragma unroll
    for (int ih = 0; ih < 4; ih++) {
      const int x = 16 * (16 * ww + g + 8 * (ih & 1)) + 8 * (ih >> 1) + 2 * c - 4;
      const int x2 = x + 2;
      const uint32_t p0 = lds32(ca + CA_S + s_chunk(x >> 3) + (x & 7) * 2);
      const uint32_t p1 = lds32(ca + CA_S + s_chunk(x2 >> 3) + (x2 & 7) * 2);
      acc3[2 * ih] = k1024 * (bf_lo(p0) + bf_hi(p0));
      acc3[2 * ih + 1] = k1024 * (bf_hi(p0) + bf_lo(p1));
    }
    QMMA(wgmma_rs_n16_tb<DH_V>, acc3, qa, dV + (CA_V9 >> 4) + 48, 16);
    QMMA(wgmma_rs_n16_tb<DH_V>, acc3, qb, dV + (CA_V7 >> 4) + 48, 16);
    wg_wait<0>();
    named_bar(barid, 128);
#pragma unroll
    for (int ih = 0; ih < 4; ih++) {
      const int t = 16 * (16 * ww + g + 8 * (ih & 1)) + 8 * (ih >> 1) + 2 * c;
      sts64f(ca + CA_Y3 + (t + 8 * (t >> 7)) * 4, acc3[2 * ih], acc3[2 * ih + 1]);
    }
    named_bar(barid, 128);
  }
}

__device__ __forceinline__ void conv_near(uint32_t ca, int ww, int lane, int barid, float dsk, long long t_start, int dbg) {
  if (dbg) TSTAMP(44);
  asm volatile("" : "+r"(ww), "+r"(lane));
  int g = lane >> 2, c = lane & 3;
  const uint32_t tb = ca + CA_QD + (ww >> 1) * (4 * QD_N + 80) + q_lane(QD_N, ww & 1, g, c) - 64;
  uint32_t qa[9], qb[9], qc[9];
  float acc[32];
#pragma unroll
  for (int i = 0; i < 32; i++) acc[i] = 0.f;
  QLOAD(qa, tb);
  QLOAD(qb, tb - 128);
  QLOAD(qc, tb - 256);
  const uint32_t dS = desc_lo(ca + CA_S + 9 * 64 + 32, 16);
  QMMA(wgmma_rs_n64<DH_SW64>, acc, qa, dS, 2);
  QMMA(wgmma_rs_n64<DH_SW64>, acc, qb, dS - 8, 2);
  wg_wait<1>(); QLOAD(qa, tb - 384);
  QMMA(wgmma_rs_n64<DH_SW64>, acc, qc, dS - 16, 2);
  wg_wait<1>(); QLOAD(qb, tb - 512);
  QMMA(wgmma_rs_n64<DH_SW64>, acc, qa, dS - 24, 2);
  QMMA(wgmma_rs_n64<DH_SW64>, acc, qb, dS - 32, 2);
  if (dbg) TSTAMP(45);
  asm volatile("" : "+r"(ww), "+r"(lane));
  g = lane >> 2; c = lane & 3;
  const int hi = ww >> 1;
  float yf[16];
#pragma unroll
  for (int k = 0; k < 16; k++) {
    const int t2 = 32 * (32 * hi + 8 * (k >> 2) + 2 * c + (k & 1)) + 16 * (ww & 1) + g + 8 * ((k >> 1) & 1) - 512;
    yf[k] = 0.f;
    if (hi || k >= 8) yf[k] = lds32f(ca + CA_Y2 + (t2 + 8 * (t2 >> 7)) * 4);
    if (hi) { const int t3 = t2 - 512; yf[k] += lds32f(ca + CA_Y3 + (t3 + 8 * (t3 >> 7)) * 4); }
  }
  wg_wait<0>();
  if (dbg) TSTAMP(46);
  named_bar(barid, 128);
  const uint32_t xb = ca + CA_Y2 + ((ww & 1) * 32 + lane) * 16;
#pragma unroll
  for (int i = 0; i < 4; i++) {
    if (hi == 0) asm volatile("st.shared.v4.f32 [%0], {%1,%2,%3,%4};" ::"r"(xb + i * 1024), "f"(acc[16 + 4 * i]), "f"(acc[17 + 4 * i]), "f"(acc[18 + 4 * i]), "f"(acc[19 + 4 * i]) : "memory");
    else if (i < 3) asm volatile("st.shared.v4.f32 [%0], {%1,%2,%3,%4};" ::"r"(xb + 4096 + i * 1024), "f"(acc[4 * i]), "f"(acc[4 * i + 1]), "f"(acc[4 * i + 2]), "f"(acc[4 * i + 3]) : "memory");
  }
  named_bar(barid, 128);
#pragma unroll
  for (int i = 0; i < 4; i++) {
    float p0 = 0.f, p1 = 0.f, p2 = 0.f, p3 = 0.f;
    if (hi || i > 0)
      asm volatile("ld.shared.v4.f32 {%0,%1,%2,%3}, [%4];" : "=f"(p0), "=f"(p1), "=f"(p2), "=f"(p3) : "r"(hi ? xb + i * 1024 : xb + 4096 + (i - 1) * 1024));
    yf[4 * i] += p0 + (hi ? acc[12 + 4 * i] : acc[4 * i]);
    yf[4 * i + 1] += p1 + (hi ? acc[13 + 4 * i] : acc[4 * i + 1]);
    yf[4 * i + 2] += p2 + (hi ? acc[14 + 4 * i] : acc[4 * i + 2]);
    yf[4 * i + 3] += p3 + (hi ? acc[15 + 4 * i] : acc[4 * i + 3]);
  }
#pragma unroll
  for (int ip = 0; ip < 2; ip++) {
    const int ncol = 32 * hi + 8 * (2 * ip + (lane >> 4)) + (lane & 7), ch = 4 * ncol + 2 * (ww & 1) + ((lane >> 3) & 1);
    uint32_t uu[4], zz[4];
    ldsm4t(ca + CA_S + s_chunk(ch), uu[0], uu[1], uu[2], uu[3]);
#pragma unroll
    for (int mi = 0; mi < 4; mi++) {
      const uint32_t sk = pack_bf(bf_lo(uu[mi]) * dsk, bf_hi(uu[mi]) * dsk);
      asm("add.rn.bf16x2 %0, %1, %2;" : "=r"(zz[mi]) : "r"(pack_bf(yf[8 * ip + 2 * mi], yf[8 * ip + 2 * mi + 1])), "r"(sk));
    }
    stsm4t(ca + CA_Z + ch * 16, zz[0], zz[1], zz[2], zz[3]);
  }
  if (dbg) TSTAMP(47);
  fence_async_smem();
}

__global__ void __cluster_dims__(2, 1, 1) __launch_bounds__(512, 1)
k_fused(const __grid_constant__ CUtensorMap tm_wg, const __grid_constant__ CUtensorMap tm_wu, const __grid_constant__ CUtensorMap tm_hst,
        const __grid_constant__ CUtensorMap tm_h, const __grid_constant__ CUtensorMap tm_wd, const __grid_constant__ CUtensorMap tm_s,
        const __grid_constant__ CUtensorMap tm_z, const __grid_constant__ CUtensorMap tm_x, const __grid_constant__ CUtensorMap tm_out, const __nv_bfloat16* __restrict__ x,
        const __nv_bfloat16* __restrict__ logA, const __nv_bfloat16* __restrict__ Aim, const __nv_bfloat16* __restrict__ Cre,
        const __nv_bfloat16* __restrict__ Cim, const __nv_bfloat16* __restrict__ logdt, const __nv_bfloat16* __restrict__ Dsk) {
  extern __shared__ __align__(1024) uint8_t smem_raw[];
  const long long t_start = 0;
  const uint32_t sb = smem_u32(smem_raw);
  const uint32_t sBar = sb + SM_BAR;
  const int tid = threadIdx.x, warp = tid >> 5, lane = tid & 31;
  const int bid = blockIdx.x, rank = bid & 1;
  const int rb = bid >> 3, nb = bid & 7;
  const int nb2 = (bid >> 1) & 3;
  const int d0 = bid * 4;
  const int wgid = warp >> 2, ww = warp & 3, g = lane >> 2, c = lane & 3;
#define BAR(i) (sBar + (i) * 8)
  float kacc[5][4], acc2048 = 0.f, kscale = 1.f;
  if (warp >= 12) {
    const int bi = (ww - 1) * 16 + lane;
    if (tid == 384) {
      for (int i = 0; i < 4; i++) mbar_init(BAR(B_XIN + i), 1);
      asm volatile("fence.mbarrier_init.release.cluster;" ::: "memory");
      TSTAMP(20);
#pragma unroll 1
      for (int j = 0; j < 8; j++) {
        if (!(j & 1)) mbar_expect(BAR(B_XIN + (j >> 1)), 32768);
        tma2d(sb + SM_A + j * 16384, &tm_x, BAR(B_XIN + (j >> 1)), 64 * j, rb * 128);
      }
      TSTAMP(21);
    }
    if (ww > 0 && lane < 16 && bi < B_COUNT) {
      int cnt;
      if (bi < B_G1E) cnt = 1;
      else if (bi < B_ARDY) cnt = 2;
      else if (bi < B_CFREE) cnt = 4;
      else if (bi < B_PUB) cnt = 6;
      else if (bi == B_PUB) cnt = 4;
      else if (bi < B_PREP) cnt = 1;
      else if (bi < B_G2F) cnt = 4;
      else if (bi <= B_G1DONE) cnt = 2;
      else if (bi < B_HSTDONE) cnt = 4;
      else if (bi == B_HSTDONE) cnt = 2;
      else if (bi < B_CV23) cnt = 4;
      else if (bi < B_ZFULL) cnt = 2;
      else if (bi == B_KGDONE) cnt = 8;
      else cnt = 1;
      mbar_init(BAR(bi), cnt);
      if (bi == B_REDFULL) mbar_expect(BAR(bi), 32768);
      asm volatile("fence.mbarrier_init.release.cluster;" ::: "memory");
    }
    if (tid >= 480 && tid < 484) sts32(sb + SM_BAR + 448 + (tid - 480) * 4, 0);
    named_bar(4, 128);
    if (tid == 384) TSTAMP(26);
    asm volatile("bar.arrive 0, 384;" ::: "memory");
    asm volatile("bar.arrive 5, 256;" ::: "memory");
    if (tid == 384) TSTAMP(27);
  } else {
    const int d = d0 + ww;
    float pa[4], pb[4], pcr[4], pci[4];
    {
      const uint2 la = __ldg((const uint2*)(logA + d * NS + 4 * lane));
      const uint2 ai = __ldg((const uint2*)(Aim + d * NS + 4 * lane));
      const uint2 cr = __ldg((const uint2*)(Cre + d * NS + 4 * lane));
      const uint2 ci = __ldg((const uint2*)(Cim + d * NS + 4 * lane));
      const float dt = bfr(expf(ldbf(logdt + d)));
      const float lav[4] = {bf_lo(la.x), bf_hi(la.x), bf_lo(la.y), bf_hi(la.y)};
      const float aiv[4] = {bf_lo(ai.x), bf_hi(ai.x), bf_lo(ai.y), bf_hi(ai.y)};
      const float crv[4] = {bf_lo(cr.x), bf_hi(cr.x), bf_lo(cr.y), bf_hi(cr.y)};
      const float civ[4] = {bf_lo(ci.x), bf_hi(ci.x), bf_lo(ci.y), bf_hi(ci.y)};
#pragma unroll
      for (int i = 0; i < 4; i++) {
        pa[i] = (-bfr(expf(lav[i])) * dt) * 1.4426950408889634f;
        pb[i] = (aiv[i] * dt) * 0.15915494309189535f;
        pcr[i] = 2.0f * (crv[i] * dt);
        pci[i] = 2.0f * (civ[i] * dt);
      }
    }
    float cmax = 0.f;
#pragma unroll
    for (int i = 0; i < 4; i++) cmax = fmaxf(cmax, fmaxf(fabsf(pcr[i]), fabsf(pci[i])));
#pragma unroll
    for (int o = 16; o > 0; o >>= 1) cmax = fmaxf(cmax, __shfl_xor_sync(0xffffffffu, cmax, o));
    const uint32_t ce = min(max(__float_as_uint(cmax) >> 23, 2u), 252u);
    const float cs = __uint_as_float((253u - ce) << 23);
    kscale = __uint_as_float((ce + 1u) << 23);
#pragma unroll
    for (int i = 0; i < 4; i++) { pcr[i] *= cs; pci[i] *= cs; }
    uint32_t pc[4];
#pragma unroll
    for (int i = 0; i < 4; i++) pc[i] = pack_h2(pcr[i], pci[i]);
    if (tid == 0) TSTAMP(25);
#pragma unroll
    for (int i = 0; i < 5; i++) { kacc[i][0] = kacc[i][1] = kacc[i][2] = kacc[i][3] = 0.f; }
    const float pg = (float)g, pg8 = (float)(g + 8);
    if (wgid == 2) named_bar(5, 256); else named_bar(0, 384);
    if (wgid < 2) {
    {
      float g0[4] = {0.f, 0.f, 0.f, 0.f}, g1[4] = {0.f, 0.f, 0.f, 0.f};
      const uint32_t one = g == 0 ? 0x3f803f80u : 0u;
      {
        const int lr = (lane & 7) + 8 * ((lane >> 3) & 1);
        const uint32_t lb = sb + SM_A + (warp * 16 + lr) * 128;
        const uint32_t kx = (uint32_t)(lane >> 4), sw = (uint32_t)(lr & 7);
#pragma unroll 1
        for (int ch = 0; ch < 8; ch += 2) {
          uint32_t a[8][4];
          mbar_wait(BAR(B_XIN + (ch >> 1)), 0);
          if (tid == 0 && ch == 6) TSTAMP(23);
#pragma unroll
          for (int k = 0; k < 8; k++)
            asm volatile("ldmatrix.sync.aligned.m8n8.x4.shared.b16 {%0,%1,%2,%3}, [%4];" : "=r"(a[k][0]), "=r"(a[k][1]), "=r"(a[k][2]), "=r"(a[k][3])
                         : "r"(lb + (ch + (k >> 2)) * 16384 + ((((k & 3) * 2 + kx) ^ sw) << 4)));
#pragma unroll
          for (int k = 0; k < 8; k++) {
            mma_bf16(g0, a[k][0], one, a[k][2], one, a[k][0], a[k][2]);
            mma_bf16(g1, a[k][1], one, a[k][3], one, a[k][1], a[k][3]);
          }
        }
      }
      float qa = (g & 1) ? g0[1] : g0[0], qb = (g & 1) ? g1[1] : g1[0];
      qa = __shfl_sync(0xffffffffu, qa, 4 * g + (g >> 1));
      qb = __shfl_sync(0xffffffffu, qb, 4 * g + (g >> 1));
      float sa0 = __shfl_sync(0xffffffffu, g0[2], g >> 1), sa1 = __shfl_sync(0xffffffffu, g0[3], g >> 1);
      float sb0 = __shfl_sync(0xffffffffu, g1[2], g >> 1), sb1 = __shfl_sync(0xffffffffu, g1[3], g >> 1);
      const float sma = (g & 1) ? sa1 : sa0, smb = (g & 1) ? sb1 : sb0;
#pragma unroll 1
      for (int u = 0; u < 2; u++) {
        const float mean = (u ? smb : sma) * (1.0f / DM);
        const float var = fmaxf(fmaf(-mean, mean, (u ? qb : qa) * (1.0f / DM)), 0.f);
        const uint32_t mb2 = pack_bf(mean, mean);
        float sq, rinv;
        asm("sqrt.approx.ftz.f32 %0, %1;" : "=f"(sq) : "f"(bfr(bfr(var) + 1e-5f)));
        asm("rcp.approx.ftz.f32 %0, %1;" : "=f"(rinv) : "f"(bfr(sq)));
        const float rh = bfr(rinv);
        const uint32_t rh2 = pack_bf(rh, rh), rl2 = pack_bf(rinv - rh, rinv - rh);
        const uint32_t rbase = sb + SM_A + (warp * 16 + u * 8 + g) * 128;
        const uint32_t o0 = (uint32_t)(((c + 4 * (g & 1)) ^ g) << 4), o1 = o0 ^ 64;
#pragma unroll 1
        for (int j = 0; j < 2; j++) {
          const uint32_t cur = rbase + j * 65536;
          uint4 vv[8];
#pragma unroll
          for (int k = 0; k < 8; k++) vv[k] = lds128(cur + (k >> 1) * 16384 + ((k & 1) ? o1 : o0));
#pragma unroll
          for (int k = 0; k < 8; k++) {
            uint32_t w[4] = {vv[k].x, vv[k].y, vv[k].z, vv[k].w};
#pragma unroll
            for (int i = 0; i < 4; i++) {
              uint32_t dpk, t;
              asm("sub.rn.bf16x2 %0, %1, %2;" : "=r"(dpk) : "r"(w[i]), "r"(mb2));
              asm("mul.rn.bf16x2 %0, %1, %2;" : "=r"(t) : "r"(dpk), "r"(rl2));
              asm("fma.rn.bf16x2 %0, %1, %2, %3;" : "=r"(w[i]) : "r"(dpk), "r"(rh2), "r"(t));
            }
            sts128(cur + (k >> 1) * 16384 + ((k & 1) ? o1 : o0), w[0], w[1], w[2], w[3]);
          }
        }
      }
    }
    fence_async_smem();
    __syncwarp();
    if (lane == 0) mbar_arrive(BAR(B_ARDY + wgid));
    if (tid == 0) TSTAMP(0);
    }
    int* const ticket = (int*)(smem_raw + SM_BAR + 448) + ww;
    int knext = 0;
    if (lane == 0) knext = atomicAdd(ticket, 1);
    {
#pragma unroll 1
      while (true) {
        const int kh = __shfl_sync(0xffffffffu, knext, 0);
        if (kh >= 16) break;
        if (lane == 0) knext = atomicAdd(ticket, 1);
        const int src = 8 * c + (kh >> 1);
        const bool hf = kh & 1;
        uint32_t fa[4][4], gb[5][2];
#pragma unroll
        for (int md = 0; md < 2; md++) {
          const float a2 = __shfl_sync(0xffffffffu, hf ? pa[2 + md] : pa[md], src), b2 = __shfl_sync(0xffffffffu, hf ? pb[2 + md] : pb[md], src);
          const uint32_t pcs = __shfl_sync(0xffffffffu, hf ? pc[2 + md] : pc[md], src);
          const float2 cc = __half22float2(*reinterpret_cast<const __half2*>(&pcs));
          const float c2r = cc.x, c2i = cc.y;
          float vr, vi, wr, wi;
          cexp_p(a2, b2, pg, vr, vi);
          cexp_p(a2, b2, pg8, wr, wi);
#pragma unroll
          for (int lv = 0; lv < 4; lv++) {
            fa[lv][2 * md] = pack_h2(vr, vi); fa[lv][2 * md + 1] = pack_h2(wr, wi);
            csq(vr, vi); csq(wr, wi);
          }
          gb[0][md] = pack_h2(fmaf(c2r, vr, -c2i * vi), fmaf(-c2r, vi, -c2i * vr));
#pragma unroll
          for (int lv = 0; lv < 4; lv++) {
            gb[lv + 1][md] = pack_h2(fmaf(c2r, wr, -c2i * wi), fmaf(-c2r, wi, -c2i * wr));
            csq(wr, wi);
          }
          acc2048 += fmaf(c2r, wr, -c2i * wi);
        }
        mma_f16(kacc[0], fa[0], gb[0]);
        mma_f16(kacc[1], fa[0], gb[1]);
        mma_f16(kacc[2], fa[1], gb[2]);
        mma_f16(kacc[3], fa[2], gb[3]);
        mma_f16(kacc[4], fa[3], gb[4]);
      }
    }
    acc2048 += __shfl_xor_sync(0xffffffffu, acc2048, 1);
    acc2048 += __shfl_xor_sync(0xffffffffu, acc2048, 2);
  }

  if (wgid < 2) {
    const int wg = __shfl_sync(0xffffffffu, (int)(threadIdx.x >> 7), 0);
    uint32_t peer_sb;
    asm volatile("mapa.shared::cluster.u32 %0, %1, %2;" : "=r"(peer_sb) : "r"(sb), "r"(rank ^ 1));
    {
      float* kv = (float*)(smem_raw + SM_KV + (wg * 4 + ww) * KV_BYTES) + 32 * c + g;
#pragma unroll
      for (int t = 0; t < 5; t++) { kv[t * 128] = kacc[t][0]; kv[t * 128 + 16] = kacc[t][1]; kv[t * 128 + 8] = kacc[t][2]; kv[t * 128 + 24] = kacc[t][3]; }
      if (lane == 0) kv[640] = acc2048;
      __syncwarp();
      if (lane == 0) mbar_arrive(BAR(B_KGDONE));
      if (tid == 0) TSTAMP(10);
    }
    asm volatile("setmaxnreg.inc.sync.aligned.u32 208;");
    mbar_wait(BAR(B_ARDY + wg), 0);
    if (tid == 0) TSTAMP(1);
    {
      float accg[88], accu[88];
      const uint32_t descA0 = desc_lo(sb + SM_A + wg * 8192, 16);
#pragma unroll 1
      for (int it = 0; it < 16; it++) {
        const int s = g1_slot(it);
        mbar_wait(BAR(B_G1F + s), g1_use(it) & 1);
        if (tid == 0 && (it & 1) == 0) TSTAMP(48 + (it >> 1));
        wg_fence();
        const uint32_t da = descA0 + (it >> 1) * 1024 + (it & 1) * 4;
        const uint32_t dg = desc_lo(sb + g1_off(s), 4096);
#pragma unroll
        for (int kk = 0; kk < 2; kk++) {
          wgmma_ss_n176_tb<DH_SW128, DH_SW128>(accg, da + 2 * kk, dg + 128 * kk, (it | kk) > 0);
          wgmma_ss_n176_tb<DH_SW128, DH_SW128>(accu, da + 2 * kk, dg + 768 + 128 * kk, (it | kk) > 0);
        }
        wg_commit();
        if (it > 0) {
          wg_wait<1>();
          if ((tid & 127) == 0) {
            mbar_arrive(BAR(B_G1E + g1_slot(it - 1)));
            if (it == 4) mbar_arrive(BAR(B_S3FREE));
            if (it == 8) mbar_arrive(BAR(B_CFREE + 0));
            if (it == 10) mbar_arrive(BAR(B_CFREE + 1));
            if (it == 14) mbar_arrive(BAR(B_CFREE + 2));
          }
        }
      }
      wg_wait<0>();
      if ((tid & 127) == 0) { mbar_arrive(BAR(B_G1DONE)); mbar_arrive(BAR(B_CFREE + 3)); }
      if (tid == 0) TSTAMP(2);
      uint32_t hp[44];
#pragma unroll
      for (int i = 0; i < 44; i++) {
        float ge[2];
        const uint32_t gp = pack_bf(accg[2 * i], accg[2 * i + 1]);
#pragma unroll
        for (int e = 0; e < 2; e++) {
          const float xg = e ? bf_hi(gp) : bf_lo(gp);
          const float inner = xg * fmaf(0.0356774081363001f * xg, xg, 0.7978845608028654f);
          float th;
          asm("tanh.approx.f32 %0, %1;" : "=f"(th) : "f"(inner));
          const float hx = 0.5f * xg;
          ge[e] = fmaf(hx, th, hx);
        }
        asm("mul.rn.bf16x2 %0, %1, %2;" : "=r"(hp[i]) : "r"(pack_bf(ge[0], ge[1])), "r"(pack_bf(accu[2 * i], accu[2 * i + 1])));
      }
      mbar_wait(BAR(B_G1DONE), 0);
      const uint32_t st = sb + SM_HST + wg * 22528 + (ww * 16 + (lane & 7) + 8 * ((lane >> 3) & 1)) * 352 + (lane >> 4) * 16;
#pragma unroll
      for (int i = 0; i < 22; i += 2) stsm4(st + i * 16, hp[2 * i], hp[2 * i + 1], hp[2 * i + 2], hp[2 * i + 3]);
      fence_async_smem();
      __syncwarp();
      if (lane == 0) mbar_arrive(BAR(B_HSTRDY + wg));
    }
    if (tid == 0) TSTAMP(3);
#pragma unroll 1
    for (int dl = wg; dl < 4; dl += 2) {
      mbar_wait(BAR(B_PREP + dl), 0);
      mbar_wait(BAR(B_SFULL + dl), 0);
      const float dsk = lds32f(sb + SM_CA + dl * CA_BYTES + CA_K1024 + 4);
      if (tid == 0 && dl == 0) TSTAMP(4);
      if (dl < 2) conv_far(sb + SM_CA + dl * CA_BYTES, ww, lane, 1 + wg);
      conv_near(sb + SM_CA + dl * CA_BYTES, ww, lane, 1 + wg, dsk, t_start, tid == 0 && dl == 2);
      __syncwarp();
      if (lane == 0) mbar_arrive(BAR(B_ZSTRDY + dl));
      if (tid == 0 && dl == 0) TSTAMP(12);
    }
    if (tid == 0) TSTAMP(5);
    {
      float acc[64];
      uint32_t xv[16];
      const int colb = nb2 * 128 + rank * 64 + 2 * c;
      const int row0 = rb * 128 + wg * 64 + ww * 16 + g;
#pragma unroll
      for (int i = 0; i < 8; i++) {
        xv[2 * i] = __ldg((const uint32_t*)(x + (size_t)row0 * DM + colb + 8 * i));
        xv[2 * i + 1] = __ldg((const uint32_t*)(x + (size_t)(row0 + 8) * DM + colb + 8 * i));
      }
#pragma unroll 1
      for (int it = 0; it < 10; it++) {
        const int s = it & 3;
        mbar_wait(BAR(B_G2F + s), (it >> 2) & 1);
        if (it == 0 && tid == 0) TSTAMP(6);
        wg_fence();
        const uint32_t as = sb + g2_stage_off(s);
        const uint32_t da = desc_lo(as + wg * 8192, 16);
        const uint32_t db = desc_lo(as + 16384, 8192);
        wgmma_ss_n128_tb<DH_SW128, DH_SW128>(acc, da, db, it > 0);
        wgmma_ss_n128_tb<DH_SW128, DH_SW128>(acc, da + 2, db + 128, 1);
        wgmma_ss_n128_tb<DH_SW128, DH_SW128>(acc, da + 4, db + 256, 1);
        wgmma_ss_n128_tb<DH_SW128, DH_SW128>(acc, da + 6, db + 384, 1);
        wg_commit();
        if (it > 0) {
          wg_wait<1>();
          if ((tid & 127) == 0) mbar_arrive(BAR(B_G2E + ((it - 1) & 3)));
        }
      }
      {
        mbar_wait(BAR(B_G2F + 2), 0);
        wg_fence();
        const uint32_t as = sb + g2_stage_off(2);
        const uint32_t da = desc_lo(as + wg * 8192, 16);
        const uint32_t db = desc_lo(as + 16384, 8192);
        wgmma_ss_n128_tb<DH_SW128, DH_SW128>(acc, da, db, 1);
        wgmma_ss_n128_tb<DH_SW128, DH_SW128>(acc, da + 2, db + 128, 1);
        wgmma_ss_n128_tb<DH_SW128, DH_SW128>(acc, da + 4, db + 256, 1);
        wg_commit();
      }
      wg_wait<0>();
      if (tid == 0) TSTAMP(7);
      mbar_wait_cl(BAR(B_REDRDY), 0);
      const uint32_t pr = peer_sb + SM_RED + tid * 16, pbar = peer_sb + SM_BAR + B_REDFULL * 8;
#pragma unroll
      for (int i = 0; i < 8; i++) {
        float v0, v1, v2, v3;
        if (rank == 0) { v0 = acc[32 + 4 * i]; v1 = acc[33 + 4 * i]; v2 = acc[34 + 4 * i]; v3 = acc[35 + 4 * i]; }
        else { v0 = acc[4 * i]; v1 = acc[4 * i + 1]; v2 = acc[4 * i + 2]; v3 = acc[4 * i + 3]; }
        asm volatile("st.async.shared::cluster.mbarrier::complete_tx::bytes.v4.f32 [%0], {%1,%2,%3,%4}, [%5];"
                     ::"r"(pr + i * 4096), "f"(v0), "f"(v1), "f"(v2), "f"(v3), "r"(pbar) : "memory");
      }
      mbar_wait(BAR(B_ZFULL), 0);
      mbar_wait(BAR(B_CV23), 0);
      uint32_t zz[16];
#pragma unroll
      for (int ip = 0; ip < 4; ip++) {
        const int drow = 8 * (2 * ip + (lane >> 4)) + (lane & 7);
        const int ch = 2 * ww + ((lane >> 3) & 1);
        ldsm4t(sb + SM_ZT + wg * 8192 + drow * 128 + ((ch ^ (drow & 7)) << 4), zz[4 * ip], zz[4 * ip + 1], zz[4 * ip + 2], zz[4 * ip + 3]);
      }
      mbar_wait_cl(BAR(B_REDFULL), 0);
      if (tid == 0) TSTAMP(8);
#pragma unroll
      for (int i = 0; i < 8; i++) {
        float p0, p1, p2, p3;
        asm volatile("ld.shared.v4.f32 {%0,%1,%2,%3}, [%4];" : "=f"(p0), "=f"(p1), "=f"(p2), "=f"(p3) : "r"(sb + SM_RED + i * 4096 + tid * 16));
        float v[4];
        if (rank == 0) { v[0] = acc[4 * i]; v[1] = acc[4 * i + 1]; v[2] = acc[4 * i + 2]; v[3] = acc[4 * i + 3]; }
        else { v[0] = acc[32 + 4 * i]; v[1] = acc[33 + 4 * i]; v[2] = acc[34 + 4 * i]; v[3] = acc[35 + 4 * i]; }
        v[0] += p0; v[1] += p1; v[2] += p2; v[3] += p3;
#pragma unroll
        for (int hh = 0; hh < 2; hh++) {
          uint32_t xz;
          asm("add.rn.bf16x2 %0, %1, %2;" : "=r"(xz) : "r"(xv[2 * i + hh]), "r"(zz[2 * i + hh]));
          asm("add.rn.bf16x2 %0, %1, %2;" : "=r"(zz[2 * i + hh]) : "r"(xz), "r"(pack_bf(v[2 * hh], v[2 * hh + 1])));
        }
      }
      {
        const int orow = ww * 16 + (lane & 7) + 8 * ((lane >> 3) & 1);
        const uint32_t ob = sb + SM_OUT + wg * 8192 + orow * 128;
#pragma unroll
        for (int ip = 0; ip < 4; ip++)
          stsm4(ob + (((2 * ip + (lane >> 4)) ^ (orow & 7)) << 4), zz[4 * ip], zz[4 * ip + 1], zz[4 * ip + 2], zz[4 * ip + 3]);
        fence_async_smem();
        named_bar(1 + wg, 128);
        if ((tid & 127) == 0) {
          tma2d_store(&tm_out, sb + SM_OUT + wg * 8192, nb2 * 128 + rank * 64, rb * 128 + wg * 64);
          bulk_commit();
          bulk_wait_read0();
        }
      }
      if (tid == 0) TSTAMP(9);
    }
  } else if (wgid == 2) {
    asm volatile("setmaxnreg.dec.sync.aligned.u32 72;");
    int st = tid - 256;
    const float dskv = ldbf(Dsk + d0 + (st & 3));
    if (tid == 256) TSTAMP(31);
    mbar_wait(BAR(B_ARDY), 0);
    mbar_wait(BAR(B_ARDY + 1), 0);
#pragma unroll 2
    for (int dblk = 0; dblk < 8; dblk++) {
      const int row = ww * 32 + lane;
      uint32_t r0, r1, r2, r3;
      ldsm4t(sb + SM_A + nb * 16384 + row * 128 + ((dblk ^ (row & 7)) << 4), r0, r1, r2, r3);
      uint32_t* dst = (uint32_t*)(g_xnT + (size_t)(nb * 64 + dblk * 8 + g) * SL + rb * 128 + ww * 32 + 2 * c);
      dst[0] = r0; dst[4] = r1; dst[8] = r2; dst[12] = r3;
    }
    __syncwarp();
    if (lane == 0) {
      for (int i = 0; i < 5; i++) mbar_arrive(BAR(B_CFREE + i));
      mbar_arrive(BAR(B_PUB));
    }
    mbar_wait(BAR(B_KGDONE), 0);
    {
      float* kv = (float*)(smem_raw + SM_KV + ww * KV_BYTES) + 32 * c + g;
#pragma unroll
      for (int t = 0; t < 5; t++) {
#pragma unroll
        for (int e = 0; e < 4; e++) {
          const int o = t * 128 + (e & 1) * 16 + (e >> 1) * 8;
          kv[o] = (kacc[t][e] + kv[o] + kv[o + KV_BYTES]) * kscale;
        }
      }
      if (lane == 0) kv[640] = (acc2048 + kv[640] + kv[640 + KV_BYTES]) * kscale;
    }
    if (tid == 256) TSTAMP(32);
    named_bar(3, 128);
#pragma unroll 1
    for (int dl = 0; dl < 4; dl++) {
      const uint32_t ca = sb + SM_CA + dl * CA_BYTES;
      const float* kv = (const float*)(smem_raw + SM_KV + dl * KV_BYTES);
      asm volatile("" : "+r"(st));
      mbar_wait(BAR(B_CFREE + dl), 0);
      if (st == 0 && dl == 3) TSTAMP(40);
      {
        unsigned short* tp = (unsigned short*)(smem_raw + SM_CA + dl * CA_BYTES);
        float v[12];
#pragma unroll
        for (int k = 0; k < 6; k++) {
          const int xx = (QD_N - 65) - (st + 128 * (k % 3)), l = xx + 256;
          const int ki = k < 3 ? min(max(xx, 0), 255) : min(128 + ((l + ((l >> 1) & 1)) >> 1), 384);
          v[k] = kv[ki];
          if (xx < 0 || xx > (k < 3 ? 255 : 258)) v[k] = 0.f;
        }
#pragma unroll
        for (int k = 0; k < 6; k++) {
          const int n = k < 4 ? Q2_N : Q3_N;
          const int m = (n - 65) - (st + (k < 4 ? 128 * (k & 1) : 0));
          const int lo = k < 2 ? 1 : 0, base = k < 2 ? 384 : (k < 4 ? 385 : (k == 4 ? 514 : 513));
          v[6 + k] = kv[base + 2 * min(max(m, lo), lo + 63)];
          if (m < lo || m > lo + 63) v[6 + k] = 0.f;
        }
#pragma unroll
        for (int k = 0; k < 6; k++) {
          const int j = (CA_QD + (k / 3) * (4 * QD_N + 80)) / 2 + st + 128 * (k % 3);
          const unsigned short h = __bfloat16_as_ushort(__float2bfloat16_rn(v[k]));
          tp[j] = h; tp[QD_N + 33 + j] = h;
        }
#pragma unroll
        for (int k = 0; k < 6; k++) {
          const int n = k < 4 ? Q2_N : Q3_N;
          const int j = st + (k < 4 ? 128 * (k & 1) : 0);
          const int off = (k < 2 ? CA_Q2E : (k < 4 ? CA_Q2O : (k == 4 ? CA_Q3E : CA_Q3O))) / 2 + j;
          const unsigned short h = __bfloat16_as_ushort(__float2bfloat16_rn(v[6 + k]));
          if (j < n) { tp[off] = h; tp[off + n + 33] = h; }
        }
        if (st < Q3_N - 128) {
          tp[CA_Q3E / 2 + 128 + st] = 0; tp[CA_Q3E / 2 + 128 + st + Q3_N + 33] = 0;
          tp[CA_Q3O / 2 + 128 + st] = 0; tp[CA_Q3O / 2 + 128 + st + Q3_N + 33] = 0;
        }
      }
      if (st == 0) sts32f(ca + CA_K1024, kv[512]);
      if (st == 32 + dl) sts32f(ca + CA_K1024 + 4, dskv);
      if (st == 0 && dl == 3) TSTAMP(41);
      mbar_wait(BAR(B_SFULL + dl), 0);
      if (st == 0 && dl == 3) TSTAMP(42);
      if (st <= 96) {
        const int ch0 = 2 * (st - 1) - 1;
        float P[33];
        P[0] = 0.f;
#pragma unroll
        for (int k = 0; k < 4; k++) {
          const int ch = ch0 + k;
          const uint4 u4 = lds128(ca + CA_S + s_chunk(ch));
          const uint32_t w[4] = {u4.x, u4.y, u4.z, u4.w};
#pragma unroll
          for (int i = 0; i < 4; i++) {
            P[8 * k + 2 * i + 1] = P[8 * k + 2 * i] + bf_lo(w[i]);
            P[8 * k + 2 * i + 2] = P[8 * k + 2 * i + 1] + bf_hi(w[i]);
          }
        }
        const int s0 = 16 * (st - 1);
        uint32_t o[8];
#pragma unroll
        for (int i = 0; i < 8; i++) o[i] = pack_bf(P[8 + 2 * i + 3] - P[8 + 2 * i - 2], P[8 + 2 * i + 4] - P[8 + 2 * i - 1]);
        sts128(ca + CA_V5 + (s0 + 512) * 2, o[0], o[1], o[2], o[3]);
        sts128(ca + CA_V5 + (s0 + 520) * 2, o[4], o[5], o[6], o[7]);
#pragma unroll
        for (int i = 0; i < 8; i++) o[i] = pack_bf(P[4 + 2 * i + 2] - P[4 + 2 * i - 1], P[4 + 2 * i + 3] - P[4 + 2 * i]);
        sts128(ca + CA_V3 + (s0 + 512) * 2, o[0], o[1], o[2], o[3]);
        sts128(ca + CA_V3 + (s0 + 520) * 2, o[4], o[5], o[6], o[7]);
        if (st < 64) {
#pragma unroll
          for (int i = 0; i < 8; i++) o[i] = pack_bf(P[8 + 2 * i + 5] - P[8 + 2 * i - 4], P[8 + 2 * i + 6] - P[8 + 2 * i - 3]);
          sts128(ca + CA_V9 + st * 16, o[0], o[1], o[2], o[3]);
          sts128(ca + CA_V9 + 1024 + st * 16, o[4], o[5], o[6], o[7]);
        }
        if (st <= 64) {
#pragma unroll
          for (int i = 0; i < 8; i++) o[i] = pack_bf(P[8 + 2 * i + 4] - P[8 + 2 * i - 3], P[8 + 2 * i + 5] - P[8 + 2 * i - 2]);
          if (st >= 1) sts128(ca + CA_V7 + 1024 + (st - 1) * 16, o[0], o[1], o[2], o[3]);
          if (st < 64) sts128(ca + CA_V7 + st * 16, o[4], o[5], o[6], o[7]);
        }
      } else {
        const int r = (st - 97) * 2;
        sts128(ca + CA_V5 + r * 16, 0, 0, 0, 0); sts128(ca + CA_V5 + r * 16 + 16, 0, 0, 0, 0);
        sts128(ca + CA_V3 + r * 16, 0, 0, 0, 0); sts128(ca + CA_V3 + r * 16 + 16, 0, 0, 0, 0);
      }
      fence_async_smem();
      if (st == 0 && dl == 3) TSTAMP(43);
      if (dl >= 2) {
        named_bar(3, 128);
        mbar_wait(BAR(B_G1DONE), 0);
        conv_far(ca, ww, lane, 3);
      }
      __syncwarp();
      if (lane == 0) mbar_arrive(BAR(B_PREP + dl));
      if (st == 0) TSTAMP(33 + dl);
    }
  } else {
    asm volatile("setmaxnreg.dec.sync.aligned.u32 24;");
    if (tid == 384) TSTAMP(29);
    if (ww == 0) {
      if (lane == 0) {
        const int n0 = nb * 176;
        mbar_wait(BAR(B_XIN + 3), 0);
#pragma unroll 1
        for (int it = 0; it < 16; it++) {
          const int s = g1_slot(it), us = g1_use(it);
          if (it == 6) mbar_wait(BAR(B_S3FREE), 0);
          if (us > 0) mbar_wait(BAR(B_G1E + s), (us - 1) & 1);
          mbar_expect(BAR(B_G1F + s), G1_STAGE_BYTES);
          const uint32_t dst = sb + g1_off(s);
#pragma unroll
          for (int b = 0; b < 3; b++) {
            tma2d(dst + b * 4096, &tm_wg, BAR(B_G1F + s), n0 + 64 * b, 32 * it);
            tma2d(dst + 12288 + b * 4096, &tm_wu, BAR(B_G1F + s), n0 + 64 * b, 32 * it);
          }
          if (it == 0) TSTAMP(22);
          if (it == 2) TSTAMP(24);
        }
        mbar_wait(BAR(B_G1DONE), 0);
#pragma unroll 1
        for (int it = 0; it < 11; it++) {
          const int s = it & 3;
          if (it == 1) mbar_wait(BAR(B_HSTDONE), 0);
          if (it == 3) mbar_wait(BAR(B_CV01), 0);
          if (it >= 4) mbar_wait(BAR(B_G2E + s), ((it >> 2) - 1) & 1);
          mbar_expect(BAR(B_G2F + s), 16384);
          const uint32_t dst = sb + g2_stage_off(s) + 16384;
          tma2d(dst, &tm_wd, BAR(B_G2F + s), nb2 * 128, rank * 688 + 64 * it);
          tma2d(dst + 8192, &tm_wd, BAR(B_G2F + s), nb2 * 128 + 64, rank * 688 + 64 * it);
        }
      }
    } else {
      if (lane == 0) {
        if (ww == 1) {
          mbar_wait(BAR(B_XIN + 3), 0);
    {
#pragma unroll 1
      for (int b = 0; b < 3; b++) {
        tma_prefetch2d(&tm_wg, nb * 176 + 64 * b, 32 * rb);
        tma_prefetch2d(&tm_wu, nb * 176 + 64 * b, 32 * rb);
      }
      if (rb < 11) {
        tma_prefetch2d(&tm_wd, nb2 * 128, rank * 688 + 64 * rb);
        tma_prefetch2d(&tm_wd, nb2 * 128 + 64, rank * 688 + 64 * rb);
      }
    }
          mbar_wait(BAR(B_PUB), 0);
          flag_add(&g_flags.xn_cnt[nb * 32]);
          flag_wait(&g_flags.xn_cnt[(d0 >> 6) * 32], 16);
          TSTAMP(16);
#pragma unroll 1
          for (int dl = 0; dl < 4; dl++) {
            mbar_wait(BAR(B_CFREE + dl), 0);
            mbar_expect(BAR(B_SFULL + dl), S_BYTES);
            tma3d(sb + SM_CA + dl * CA_BYTES + CA_S, &tm_s, BAR(B_SFULL + dl), 0, -9, d0 + dl);
          }
          mbar_wait(BAR(B_G1DONE), 0);
          flag_poll(&g_flags.h_flag[(bid ^ 1) * 8], 2);
#pragma unroll 1
          for (int t = rank * 3; t < rank * 4 + 4; t++) flag_poll(&g_flags.h_flag[(rb * 8 + t) * 8], 2);
          flag_fence();
          mbar_arrive(BAR(B_PEERUP));
#pragma unroll 1
          for (int it = 0; it < 11; it++) {
            const int s = it & 3;
            const int k0 = rank * 688 + 64 * it;
            if (it == 0) TSTAMP(17);
            if (it == 0) mbar_wait(BAR(B_HSTDONE), 0);
            if (it == 3) mbar_wait(BAR(B_CV01), 0);
            if (it >= 4) mbar_wait(BAR(B_G2E + s), ((it >> 2) - 1) & 1);
            mbar_expect(BAR(B_G2F + s), 16384);
            tma2d(sb + g2_stage_off(s), &tm_h, BAR(B_G2F + s), k0, rb * 128);
          }
          mbar_arrive(BAR(B_HLDONE));
        } else {
          const int w2 = ww - 2;
          mbar_wait(BAR(B_HSTRDY + w2), 0);
          tma2d_store(&tm_hst, sb + SM_HST + w2 * 22528, nb * 176, rb * 128 + w2 * 64);
          bulk_commit();
          bulk_wait_read0();
          mbar_arrive(BAR(B_HSTDONE));
          bulk_wait0();
          flag_add(&g_flags.h_flag[(rb * 8 + nb) * 8]);
          if (w2 == 0) TSTAMP(19);
#pragma unroll 1
          for (int dl = w2; dl < 4; dl += 2) {
            mbar_wait(BAR(B_ZSTRDY + dl), 0);
            bulk_store(g_zT + (size_t)(d0 + dl) * SL, sb + SM_CA + dl * CA_BYTES + CA_Z, 4096);
            bulk_commit();
            bulk_wait_read0();
            mbar_arrive(BAR(dl >= 2 ? B_CV23 : B_CV01));
            bulk_wait0();
            flag_add(&g_flags.z_cnt[(d0 >> 6) * 32]);
          }
          if (w2 == 1) {
          mbar_wait(BAR(B_PREP + 3), 0);
          flag_wait(&g_flags.z_cnt[(nb2 * 2 + rank) * 32], 64);
          TSTAMP(18);
          mbar_expect(BAR(B_ZFULL), 16384);
          tma2d(sb + SM_ZT, &tm_z, BAR(B_ZFULL), rb * 128, nb2 * 128 + rank * 64);
          tma2d(sb + SM_ZT + 8192, &tm_z, BAR(B_ZFULL), rb * 128 + 64, nb2 * 128 + rank * 64);
          mbar_wait(BAR(B_HLDONE), 0);
          unsigned prev;
          asm volatile("atom.acq_rel.gpu.global.add.u32 %0, [%1], 1;" : "=r"(prev) : "l"(&g_flags.done) : "memory");
          if (prev == 127) {
            for (int i = 0; i < 8; i++) { g_flags.xn_cnt[i * 32] = 0; g_flags.z_cnt[i * 32] = 0; }
            for (int i = 0; i < 128; i++) g_flags.h_flag[i * 8] = 0;
            g_flags.done = 0;
          }
          }
          if (w2 == 0) {
            mbar_wait(BAR(B_CV23), 0);
            mbar_wait(BAR(B_PEERUP), 0);
            uint32_t peer_bar;
            asm volatile("mapa.shared::cluster.u32 %0, %1, %2;" : "=r"(peer_bar) : "r"(BAR(B_REDRDY)), "r"(rank ^ 1));
            mbar_arrive_remote(peer_bar);
          }
        }
      }
    }
  }
}

typedef CUresult (*EncFn)(CUtensorMap*, CUtensorMapDataType, cuuint32_t, void*, const cuuint64_t*, const cuuint64_t*, const cuuint32_t*,
                          const cuuint32_t*, CUtensorMapInterleave, CUtensorMapSwizzle, CUtensorMapL2promotion, CUtensorMapFloatOOBfill);

static void make_map(EncFn enc, CUtensorMap* tm, void* ptr, uint64_t cols, uint64_t rows, uint32_t bc, uint32_t br, CUtensorMapSwizzle sw) {
  cuuint64_t gd[2] = {cols, rows};
  cuuint64_t gs[1] = {cols * 2};
  cuuint32_t bd[2] = {bc, br};
  cuuint32_t es[2] = {1, 1};
  enc(tm, CU_TENSOR_MAP_DATA_TYPE_BFLOAT16, 2, ptr, gd, gs, bd, es, CU_TENSOR_MAP_INTERLEAVE_NONE, sw, CU_TENSOR_MAP_L2_PROMOTION_L2_128B,
      CU_TENSOR_MAP_FLOAT_OOB_FILL_NONE);
}

extern "C" void kernel_launch(void* const* d_in, const int* in_sizes, int n_in, void* d_out, int out_size) {
  const __nv_bfloat16* u = (const __nv_bfloat16*)d_in[0];
  static EncFn enc = nullptr;
  static void *h_ptr = nullptr, *xnT_ptr = nullptr, *zT_ptr = nullptr;
  if (!enc) {
    cudaDriverEntryPointQueryResult qr;
    cudaGetDriverEntryPoint("cuTensorMapEncodeTiled", (void**)&enc, cudaEnableDefault, &qr);
    cudaGetSymbolAddress(&h_ptr, g_h);
    cudaGetSymbolAddress(&xnT_ptr, g_xnT);
    cudaGetSymbolAddress(&zT_ptr, g_zT);
    cudaFuncSetAttribute(k_fused, cudaFuncAttributeMaxDynamicSharedMemorySize, SM_TOTAL);
  }
  CUtensorMap tm_wg, tm_wu, tm_hst, tm_h, tm_wd, tm_s, tm_z, tm_x, tm_out;
  make_map(enc, &tm_out, d_out, DM, SL, 64, 64, CU_TENSOR_MAP_SWIZZLE_128B);
  make_map(enc, &tm_x, d_in[0], DM, SL, 64, 128, CU_TENSOR_MAP_SWIZZLE_128B);
  make_map(enc, &tm_wg, d_in[8], FF, DM, 64, 32, CU_TENSOR_MAP_SWIZZLE_128B);
  make_map(enc, &tm_wu, d_in[9], FF, DM, 64, 32, CU_TENSOR_MAP_SWIZZLE_128B);
  make_map(enc, &tm_hst, h_ptr, FF, SL, 176, 64, CU_TENSOR_MAP_SWIZZLE_NONE);
  make_map(enc, &tm_h, h_ptr, FF, SL, 64, 128, CU_TENSOR_MAP_SWIZZLE_128B);
  make_map(enc, &tm_wd, d_in[10], DM, FF, 64, 64, CU_TENSOR_MAP_SWIZZLE_128B);
  make_map(enc, &tm_z, zT_ptr, SL, DM, 64, 64, CU_TENSOR_MAP_SWIZZLE_128B);
  {
    cuuint64_t gd[3] = {32, 64, (cuuint64_t)DM};
    cuuint64_t gs[2] = {64, (cuuint64_t)SL * 2};
    cuuint32_t bd[3] = {32, 73, 1};
    cuuint32_t es[3] = {1, 1, 1};
    enc(&tm_s, CU_TENSOR_MAP_DATA_TYPE_BFLOAT16, 3, xnT_ptr, gd, gs, bd, es, CU_TENSOR_MAP_INTERLEAVE_NONE, CU_TENSOR_MAP_SWIZZLE_64B,
        CU_TENSOR_MAP_L2_PROMOTION_L2_128B, CU_TENSOR_MAP_FLOAT_OOB_FILL_NONE);
  }
  k_fused<<<128, 512, SM_TOTAL, cudaStreamPerThread>>>(tm_wg, tm_wu, tm_hst, tm_h, tm_wd, tm_s, tm_z, tm_x, tm_out, u, (const __nv_bfloat16*)d_in[1],
                                                       (const __nv_bfloat16*)d_in[2], (const __nv_bfloat16*)d_in[3], (const __nv_bfloat16*)d_in[4],
                                                       (const __nv_bfloat16*)d_in[5], (const __nv_bfloat16*)d_in[6]);
}
```
